```python
import torch

def _softmax(x, axis=-1):
    return torch.softmax(x, dim=axis)
def _gelu(x):
    return torch.nn.functional.gelu(x, approximate="tanh")
def _silu(x):
    return torch.nn.functional.silu(x)
def _sigmoid(x):
    return torch.sigmoid(x)
def _layernorm(x, axis=-1, eps=1e-5):
    m = x.mean(dim=axis, keepdim=True)
    v = x.var(dim=axis, keepdim=True, unbiased=False)
    return (x - m) / torch.sqrt(v + eps)
def _scatter_add(tgt, idx, src, axis=0):
    return tgt.clone().index_add_(axis, idx, src)
def _segment_sum(src, seg, n):
    out = torch.zeros((n,) + src.shape[1:], dtype=src.dtype)
    return out.index_add_(0, seg, src)
def _pad(x, pw):
    flat = tuple(v for pair in reversed(pw) for v in pair)
    return torch.nn.functional.pad(x, flat)

kernel_name = 'concat_heads__mha_block_cached__gqa_block_cached__near_ridge'

def setup_inputs():

    _w = (lambda a: (lambda t: t.to(torch.bfloat16) if t.is_floating_point() else t)(torch.as_tensor(a)))
    def _A_setup():
        B, Sq, D = 8, 96, 640
        H, Sk, Dh = 32, 96, 192
        return {
            "x": _w((lambda *s: torch.randn(*s, dtype=torch.bfloat16) * 0.8)(B, Sq, D)),
            "k_cache": _w((lambda *s: torch.randn(*s, dtype=torch.bfloat16) * 0.8)(B, H, Sk, Dh)),
            "v_cache": _w((lambda *s: torch.randn(*s, dtype=torch.bfloat16) * 0.05)(B, H, Sk, Dh)),
            "wq": _w((lambda *s: torch.randn(*s, dtype=torch.bfloat16) * 0.8)(D, H * Dh) * (D ** -0.5)),
            "wo": _w((lambda *s: torch.randn(*s, dtype=torch.bfloat16) * 0.05)(H * Dh, D) * ((H * Dh) ** -0.5)),
        }
    _A_in = _A_setup()

    def _B_setup():
        B, Sq, D = 8, 96, 640
        Hq, Hkv, Sk, Dh = 32, 32, 96, 192
        assert Hq % Hkv == 0, (Hq, Hkv)
        return {
            "x": _w((lambda *s: torch.randn(*s, dtype=torch.bfloat16) * 0.8)(B, Sq, D)),
            "k_cache": _w((lambda *s: torch.randn(*s, dtype=torch.bfloat16) * 0.8)(B, Hkv, Sk, Dh)),
            "v_cache": _w((lambda *s: torch.randn(*s, dtype=torch.bfloat16) * 0.05)(B, Hkv, Sk, Dh)),
            "wq": _w((lambda *s: torch.randn(*s, dtype=torch.bfloat16) * 0.8)(D, Hq * Dh) * (D ** -0.5)),
            "wo": _w((lambda *s: torch.randn(*s, dtype=torch.bfloat16) * 0.05)(Hq * Dh, D) * ((Hq * Dh) ** -0.5)),
        }
    _B_in = _B_setup()

    return {
        "A_x": _A_in["x"],
        "A_k_cache": _A_in["k_cache"],
        "A_v_cache": _A_in["v_cache"],
        "A_wq": _A_in["wq"],
        "A_wo": _A_in["wo"],
        "B_x": _B_in["x"],
        "B_k_cache": _B_in["k_cache"],
        "B_v_cache": _B_in["v_cache"],
        "B_wq": _B_in["wq"],
        "B_wo": _B_in["wo"],
    }

def reference(A_x, A_k_cache, A_v_cache, A_wq, A_wo, B_x, B_k_cache, B_v_cache, B_wq, B_wo):
    def _A_ref(x, k_cache, v_cache, wq, wo):
        B, Sq, D = x.shape
        H, Dh = 32, 192
        q = (lambda x, *d: x.permute(*d))((x @ wq).reshape(B, Sq, H, Dh), 0, 2, 1, 3)
        scores = torch.einsum("bhqd,bhkd->bhqk", q, k_cache) * (Dh ** -0.5)
        p = _softmax(scores, axis=-1)
        o = torch.einsum("bhqk,bhkd->bhqd", p, v_cache)
        return (lambda x, *d: x.permute(*d))(o, 0, 2, 1, 3).reshape(B, Sq, H * Dh) @ wo

    def _B_ref(x, k_cache, v_cache, wq, wo):
        B, Sq, D = x.shape
        Hq, Dh = 32, 192
        Hkv = k_cache.shape[1]
        rep = Hq // Hkv
        q = (lambda x, *d: x.permute(*d))((x @ wq).reshape(B, Sq, Hq, Dh), 0, 2, 1, 3)
        k = (lambda x, n, axis: torch.repeat_interleave(x, n, dim=axis))(k_cache, rep, axis=1)
        v = (lambda x, n, axis: torch.repeat_interleave(x, n, dim=axis))(v_cache, rep, axis=1)
        scores = torch.einsum("bhqd,bhkd->bhqk", q, k) * (Dh ** -0.5)
        p = _softmax(scores, axis=-1)
        o = torch.einsum("bhqk,bhkd->bhqd", p, v)
        return (lambda x, *d: x.permute(*d))(o, 0, 2, 1, 3).reshape(B, Sq, Hq * Dh) @ wo

    a = _A_ref(A_x, A_k_cache, A_v_cache, A_wq, A_wo)
    b = _B_ref(B_x, B_k_cache, B_v_cache, B_wq, B_wo)
    return torch.concatenate([a, b], axis=-1)
```

```cpp
#include <cuda_runtime.h>
#include <cuda_bf16.h>
#include <cuda.h>
#include <stdint.h>

#pragma nv_diag_suppress 549
namespace {

constexpr int NB    = 8;
constexpr int SQ    = 96;
constexpr int DM    = 640;
constexpr int NH    = 32;
constexpr int DH    = 192;
constexpr int HD    = NH * DH;
constexpr int ROWS  = NB * SQ;

constexpr int PF_NA = 16, PF_NB = 24, PF_A = 950, PF_B = 500, PF_C = 1000;
constexpr int O1_STEPS = 6;
constexpr int O2_STEPS = 6;
constexpr uint32_t SPIN_LIMIT = 1u << 23;
constexpr int SLOT   = 24576;
constexpr int NSLOT  = 9;
constexpr int NSEQ   = 100;
constexpr int P2_BEG = 52;
constexpr int BAR_OFF   = NSLOT * SLOT;
constexpr int SMEM_USED = BAR_OFF + 1280;
constexpr int SMEM_DYN  = SMEM_USED + 1024;

constexpr uint32_t HI_SW128 = (1024u >> 4) | (1u << 30);
constexpr uint32_t HI_SW64  = (512u >> 4) | (2u << 30);

struct Params {
  CUtensorMap x[2], wq[2], k[2], v[2], wo[2], o;
  const __nv_bfloat16* kp[2];
  const __nv_bfloat16* vp[2];
  uint8_t* oscr;
  uint32_t zero;
  __nv_bfloat16* out;
};

constexpr int OPAGE = 2 << 20, OITEM = 18 * 8192, OPER = 14, OPAGES = (256 + OPER - 1) / OPER;
constexpr uint32_t L2_HASH = 0xB3000u;
__device__ uint8_t g_oscr[(OPAGES + 1) * (size_t)OPAGE];
__device__ unsigned g_flag[2 * 4 * NH];
__device__ unsigned g_cons[128];
__device__ unsigned g_epoch;
__device__ unsigned g_done;

__device__ __forceinline__ uint32_t smem_u32(const void* p) { return (uint32_t)__cvta_generic_to_shared(p); }
__device__ __forceinline__ void mbar_init(uint32_t bar, uint32_t cnt) { asm volatile("mbarrier.init.shared::cta.b64 [%0], %1;" ::"r"(bar), "r"(cnt)); }
__device__ __forceinline__ void mbar_expect_tx(uint32_t bar, uint32_t bytes) {
  asm volatile("mbarrier.arrive.expect_tx.shared::cta.b64 _, [%0], %1;" ::"r"(bar), "r"(bytes) : "memory");
}
__device__ __forceinline__ void mbar_arrive(uint32_t bar) { asm volatile("mbarrier.arrive.shared::cta.b64 _, [%0];" ::"r"(bar) : "memory"); }
__device__ __forceinline__ void mbar_wait(uint32_t bar, uint32_t parity) {
  asm volatile(
      "{\n.reg .pred p;\n"
      "LAB_WAIT:\n"
      "mbarrier.try_wait.parity.shared::cta.b64 p, [%0], %1;\n"
      "@!p bra LAB_WAIT;\n"
      "}" ::"r"(bar), "r"(parity) : "memory");
}
__device__ __forceinline__ void tma2_mc(uint32_t dst, const CUtensorMap* m, uint32_t bar, int c0, int c1) {
  asm volatile("cp.async.bulk.tensor.2d.shared::cluster.global.mbarrier::complete_tx::bytes.multicast::cluster [%0], [%1, {%3, %4}], [%2], %5;"
               ::"r"(dst), "l"(m), "r"(bar), "r"(c0), "r"(c1), "h"((uint16_t)3) : "memory");
}
__device__ __forceinline__ uint64_t policy_evict_first() {
  uint64_t p;
  asm volatile("createpolicy.fractional.L2::evict_first.b64 %0, 1.0;" : "=l"(p));
  return p;
}
__device__ __forceinline__ void tma3h(uint32_t dst, const CUtensorMap* m, uint32_t bar, int c0, int c1, int c2, uint64_t pol) {
  asm volatile("cp.async.bulk.tensor.3d.shared::cluster.global.mbarrier::complete_tx::bytes.L2::cache_hint [%0], [%1, {%3, %4, %5}], [%2], %6;"
               ::"r"(dst), "l"(m), "r"(bar), "r"(c0), "r"(c1), "r"(c2), "l"(pol) : "memory");
}
__device__ __forceinline__ void tma4h(uint32_t dst, const CUtensorMap* m, uint32_t bar, int c0, int c1, int c2, int c3, uint64_t pol) {
  asm volatile("cp.async.bulk.tensor.4d.shared::cluster.global.mbarrier::complete_tx::bytes.L2::cache_hint [%0], [%1, {%3, %4, %5, %6}], [%2], %7;"
               ::"r"(dst), "l"(m), "r"(bar), "r"(c0), "r"(c1), "r"(c2), "r"(c3), "l"(pol) : "memory");
}
__device__ __forceinline__ void tma5h(uint32_t dst, const CUtensorMap* m, uint32_t bar, int c0, int c1, int c2, int c3, int c4, uint64_t pol) {
  asm volatile("cp.async.bulk.tensor.5d.shared::cluster.global.mbarrier::complete_tx::bytes.L2::cache_hint [%0], [%1, {%3, %4, %5, %6, %7}], [%2], %8;"
               ::"r"(dst), "l"(m), "r"(bar), "r"(c0), "r"(c1), "r"(c2), "r"(c3), "r"(c4), "l"(pol) : "memory");
}
__device__ __forceinline__ bool elect_one() {
  uint32_t pred;
  asm volatile("{\n.reg .pred p;\nelect.sync _|p, 0xffffffff;\nselp.u32 %0, 1, 0, p;\n}" : "=r"(pred));
  return pred != 0;
}
#define WG_FENCE()  asm volatile("wgmma.fence.sync.aligned;" ::: "memory")
#define WG_COMMIT() asm volatile("wgmma.commit_group.sync.aligned;" ::: "memory")
#define WG_WAIT(n)  asm volatile("wgmma.wait_group.sync.aligned %0;" ::"n"(n) : "memory")
template <int N> __device__ __forceinline__ void fence_regs(float (&d)[N]) {
#pragma unroll
  for (int i = 0; i < N; i++) asm volatile("" : "+f"(d[i])::"memory");
}
template <int N> __device__ __forceinline__ void fence_regs(uint32_t (&d)[N]) {
#pragma unroll
  for (int i = 0; i < N; i++) asm volatile("" : "+r"(d[i])::"memory");
}
__device__ __forceinline__ uint32_t pack_bf16(float lo, float hi) {
  uint32_t r;
  asm("cvt.rn.bf16x2.f32 %0, %1, %2;" : "=r"(r) : "f"(hi), "f"(lo));
  return r;
}
__device__ __forceinline__ float ex2(float x) {
  float r;
  asm("ex2.approx.ftz.f32 %0, %1;" : "=f"(r) : "f"(x));
  return r;
}
#define LBO(bytes) (((bytes) >> 4) << 16)
__device__ __forceinline__ uint32_t dlo(uint32_t addr, uint32_t lbo) { return ((addr & 0x3FFFF) >> 4) | ((lbo >> 4) << 16); }

template <uint32_t AHI, uint32_t BHI, uint32_t AOFF, uint32_t BOFF, int SD> __device__ __forceinline__ void wg_ss_n192_tb(float (&d)[96], uint32_t alo, uint32_t blo) {
  asm volatile("{\n.reg .pred p;\n.reg .b32 ta, tb;\n.reg .b64 da, db;\nsetp.ne.b32 p, %98, 0;\nadd.u32 ta, %96, %101;\nadd.u32 tb, %97, %102;\nmov.b64 da, {ta, %99};\nmov.b64 db, {tb, %100};\n"
    "wgmma.mma_async.sync.aligned.m64n192k16.f32.bf16.bf16 "
    "{%0, %1, %2, %3, %4, %5, %6, %7, %8, %9, %10, %11, %12, %13, %14, %15, %16, %17, %18, %19, %20, %21, %22, %23, %24, %25, %26, %27, %28, %29, %30, %31, %32, %33, %34, %35, %36, %37, %38, %39, %40, %41, %42, %43, %44, %45, %46, %47, %48, %49, %50, %51, %52, %53, %54, %55, %56, %57, %58, %59, %60, %61, %62, %63, %64, %65, %66, %67, %68, %69, %70, %71, %72, %73, %74, %75, %76, %77, %78, %79, %80, %81, %82, %83, %84, %85, %86, %87, %88, %89, %90, %91, %92, %93, %94, %95}, "
    "da, db, p, 1, 1, 0, 1;\n}\n"
    : "+f"(d[0]), "+f"(d[1]), "+f"(d[2]), "+f"(d[3]), "+f"(d[4]), "+f"(d[5]), "+f"(d[6]), "+f"(d[7]), "+f"(d[8]), "+f"(d[9]), "+f"(d[10]), "+f"(d[11]), "+f"(d[12]), "+f"(d[13]), "+f"(d[14]), "+f"(d[15]), "+f"(d[16]), "+f"(d[17]), "+f"(d[18]), "+f"(d[19]), "+f"(d[20]), "+f"(d[21]), "+f"(d[22]), "+f"(d[23]), "+f"(d[24]), "+f"(d[25]), "+f"(d[26]), "+f"(d[27]), "+f"(d[28]), "+f"(d[29]), "+f"(d[30]), "+f"(d[31]), "+f"(d[32]), "+f"(d[33]), "+f"(d[34]), "+f"(d[35]), "+f"(d[36]), "+f"(d[37]), "+f"(d[38]), "+f"(d[39]), "+f"(d[40]), "+f"(d[41]), "+f"(d[42]), "+f"(d[43]), "+f"(d[44]), "+f"(d[45]), "+f"(d[46]), "+f"(d[47]), "+f"(d[48]), "+f"(d[49]), "+f"(d[50]), "+f"(d[51]), "+f"(d[52]), "+f"(d[53]), "+f"(d[54]), "+f"(d[55]), "+f"(d[56]), "+f"(d[57]), "+f"(d[58]), "+f"(d[59]), "+f"(d[60]), "+f"(d[61]), "+f"(d[62]), "+f"(d[63]), "+f"(d[64]), "+f"(d[65]), "+f"(d[66]), "+f"(d[67]), "+f"(d[68]), "+f"(d[69]), "+f"(d[70]), "+f"(d[71]), "+f"(d[72]), "+f"(d[73]), "+f"(d[74]), "+f"(d[75]), "+f"(d[76]), "+f"(d[77]), "+f"(d[78]), "+f"(d[79]), "+f"(d[80]), "+f"(d[81]), "+f"(d[82]), "+f"(d[83]), "+f"(d[84]), "+f"(d[85]), "+f"(d[86]), "+f"(d[87]), "+f"(d[88]), "+f"(d[89]), "+f"(d[90]), "+f"(d[91]), "+f"(d[92]), "+f"(d[93]), "+f"(d[94]), "+f"(d[95])
    : "r"(alo), "r"(blo), "n"(SD), "n"(AHI), "n"(BHI), "n"(AOFF), "n"(BOFF));
}
template <uint32_t AHI, uint32_t BHI, uint32_t AOFF, uint32_t BOFF, int SD> __device__ __forceinline__ void wg_ss_n160_tb(float (&d)[80], uint32_t alo, uint32_t blo) {
  asm volatile("{\n.reg .pred p;\n.reg .b32 ta, tb;\n.reg .b64 da, db;\nsetp.ne.b32 p, %82, 0;\nadd.u32 ta, %80, %85;\nadd.u32 tb, %81, %86;\nmov.b64 da, {ta, %83};\nmov.b64 db, {tb, %84};\n"
    "wgmma.mma_async.sync.aligned.m64n160k16.f32.bf16.bf16 "
    "{%0, %1, %2, %3, %4, %5, %6, %7, %8, %9, %10, %11, %12, %13, %14, %15, %16, %17, %18, %19, %20, %21, %22, %23, %24, %25, %26, %27, %28, %29, %30, %31, %32, %33, %34, %35, %36, %37, %38, %39, %40, %41, %42, %43, %44, %45, %46, %47, %48, %49, %50, %51, %52, %53, %54, %55, %56, %57, %58, %59, %60, %61, %62, %63, %64, %65, %66, %67, %68, %69, %70, %71, %72, %73, %74, %75, %76, %77, %78, %79}, "
    "da, db, p, 1, 1, 0, 1;\n}\n"
    : "+f"(d[0]), "+f"(d[1]), "+f"(d[2]), "+f"(d[3]), "+f"(d[4]), "+f"(d[5]), "+f"(d[6]), "+f"(d[7]), "+f"(d[8]), "+f"(d[9]), "+f"(d[10]), "+f"(d[11]), "+f"(d[12]), "+f"(d[13]), "+f"(d[14]), "+f"(d[15]), "+f"(d[16]), "+f"(d[17]), "+f"(d[18]), "+f"(d[19]), "+f"(d[20]), "+f"(d[21]), "+f"(d[22]), "+f"(d[23]), "+f"(d[24]), "+f"(d[25]), "+f"(d[26]), "+f"(d[27]), "+f"(d[28]), "+f"(d[29]), "+f"(d[30]), "+f"(d[31]), "+f"(d[32]), "+f"(d[33]), "+f"(d[34]), "+f"(d[35]), "+f"(d[36]), "+f"(d[37]), "+f"(d[38]), "+f"(d[39]), "+f"(d[40]), "+f"(d[41]), "+f"(d[42]), "+f"(d[43]), "+f"(d[44]), "+f"(d[45]), "+f"(d[46]), "+f"(d[47]), "+f"(d[48]), "+f"(d[49]), "+f"(d[50]), "+f"(d[51]), "+f"(d[52]), "+f"(d[53]), "+f"(d[54]), "+f"(d[55]), "+f"(d[56]), "+f"(d[57]), "+f"(d[58]), "+f"(d[59]), "+f"(d[60]), "+f"(d[61]), "+f"(d[62]), "+f"(d[63]), "+f"(d[64]), "+f"(d[65]), "+f"(d[66]), "+f"(d[67]), "+f"(d[68]), "+f"(d[69]), "+f"(d[70]), "+f"(d[71]), "+f"(d[72]), "+f"(d[73]), "+f"(d[74]), "+f"(d[75]), "+f"(d[76]), "+f"(d[77]), "+f"(d[78]), "+f"(d[79])
    : "r"(alo), "r"(blo), "n"(SD), "n"(AHI), "n"(BHI), "n"(AOFF), "n"(BOFF));
}
template <uint32_t BHI, uint32_t BOFF, int SD> __device__ __forceinline__ void wg_rs_n96(float (&d)[48], uint32_t a0, uint32_t a1, uint32_t a2, uint32_t a3, uint32_t blo) {
  asm volatile("{\n.reg .pred p;\n.reg .b32 tb;\n.reg .b64 db;\nsetp.ne.b32 p, %53, 0;\nadd.u32 tb, %52, %55;\nmov.b64 db, {tb, %54};\n"
    "wgmma.mma_async.sync.aligned.m64n96k16.f32.bf16.bf16 "
    "{%0, %1, %2, %3, %4, %5, %6, %7, %8, %9, %10, %11, %12, %13, %14, %15, %16, %17, %18, %19, %20, %21, %22, %23, %24, %25, %26, %27, %28, %29, %30, %31, %32, %33, %34, %35, %36, %37, %38, %39, %40, %41, %42, %43, %44, %45, %46, %47}, "
    "{%48, %49, %50, %51}, db, p, 1, 1, 0;\n}\n"
    : "+f"(d[0]), "+f"(d[1]), "+f"(d[2]), "+f"(d[3]), "+f"(d[4]), "+f"(d[5]), "+f"(d[6]), "+f"(d[7]), "+f"(d[8]), "+f"(d[9]), "+f"(d[10]), "+f"(d[11]), "+f"(d[12]), "+f"(d[13]), "+f"(d[14]), "+f"(d[15]), "+f"(d[16]), "+f"(d[17]), "+f"(d[18]), "+f"(d[19]), "+f"(d[20]), "+f"(d[21]), "+f"(d[22]), "+f"(d[23]), "+f"(d[24]), "+f"(d[25]), "+f"(d[26]), "+f"(d[27]), "+f"(d[28]), "+f"(d[29]), "+f"(d[30]), "+f"(d[31]), "+f"(d[32]), "+f"(d[33]), "+f"(d[34]), "+f"(d[35]), "+f"(d[36]), "+f"(d[37]), "+f"(d[38]), "+f"(d[39]), "+f"(d[40]), "+f"(d[41]), "+f"(d[42]), "+f"(d[43]), "+f"(d[44]), "+f"(d[45]), "+f"(d[46]), "+f"(d[47])
    : "r"(a0), "r"(a1), "r"(a2), "r"(a3), "r"(blo), "n"(SD), "n"(BHI), "n"(BOFF));
}
template <uint32_t BHI, uint32_t BOFF, int SD> __device__ __forceinline__ void wg_rs_n192_tb(float (&d)[96], uint32_t a0, uint32_t a1, uint32_t a2, uint32_t a3, uint32_t blo) {
  asm volatile("{\n.reg .pred p;\n.reg .b32 tb;\n.reg .b64 db;\nsetp.ne.b32 p, %101, 0;\nadd.u32 tb, %100, %103;\nmov.b64 db, {tb, %102};\n"
    "wgmma.mma_async.sync.aligned.m64n192k16.f32.bf16.bf16 "
    "{%0, %1, %2, %3, %4, %5, %6, %7, %8, %9, %10, %11, %12, %13, %14, %15, %16, %17, %18, %19, %20, %21, %22, %23, %24, %25, %26, %27, %28, %29, %30, %31, %32, %33, %34, %35, %36, %37, %38, %39, %40, %41, %42, %43, %44, %45, %46, %47, %48, %49, %50, %51, %52, %53, %54, %55, %56, %57, %58, %59, %60, %61, %62, %63, %64, %65, %66, %67, %68, %69, %70, %71, %72, %73, %74, %75, %76, %77, %78, %79, %80, %81, %82, %83, %84, %85, %86, %87, %88, %89, %90, %91, %92, %93, %94, %95}, "
    "{%96, %97, %98, %99}, db, p, 1, 1, 1;\n}\n"
    : "+f"(d[0]), "+f"(d[1]), "+f"(d[2]), "+f"(d[3]), "+f"(d[4]), "+f"(d[5]), "+f"(d[6]), "+f"(d[7]), "+f"(d[8]), "+f"(d[9]), "+f"(d[10]), "+f"(d[11]), "+f"(d[12]), "+f"(d[13]), "+f"(d[14]), "+f"(d[15]), "+f"(d[16]), "+f"(d[17]), "+f"(d[18]), "+f"(d[19]), "+f"(d[20]), "+f"(d[21]), "+f"(d[22]), "+f"(d[23]), "+f"(d[24]), "+f"(d[25]), "+f"(d[26]), "+f"(d[27]), "+f"(d[28]), "+f"(d[29]), "+f"(d[30]), "+f"(d[31]), "+f"(d[32]), "+f"(d[33]), "+f"(d[34]), "+f"(d[35]), "+f"(d[36]), "+f"(d[37]), "+f"(d[38]), "+f"(d[39]), "+f"(d[40]), "+f"(d[41]), "+f"(d[42]), "+f"(d[43]), "+f"(d[44]), "+f"(d[45]), "+f"(d[46]), "+f"(d[47]), "+f"(d[48]), "+f"(d[49]), "+f"(d[50]), "+f"(d[51]), "+f"(d[52]), "+f"(d[53]), "+f"(d[54]), "+f"(d[55]), "+f"(d[56]), "+f"(d[57]), "+f"(d[58]), "+f"(d[59]), "+f"(d[60]), "+f"(d[61]), "+f"(d[62]), "+f"(d[63]), "+f"(d[64]), "+f"(d[65]), "+f"(d[66]), "+f"(d[67]), "+f"(d[68]), "+f"(d[69]), "+f"(d[70]), "+f"(d[71]), "+f"(d[72]), "+f"(d[73]), "+f"(d[74]), "+f"(d[75]), "+f"(d[76]), "+f"(d[77]), "+f"(d[78]), "+f"(d[79]), "+f"(d[80]), "+f"(d[81]), "+f"(d[82]), "+f"(d[83]), "+f"(d[84]), "+f"(d[85]), "+f"(d[86]), "+f"(d[87]), "+f"(d[88]), "+f"(d[89]), "+f"(d[90]), "+f"(d[91]), "+f"(d[92]), "+f"(d[93]), "+f"(d[94]), "+f"(d[95])
    : "r"(a0), "r"(a1), "r"(a2), "r"(a3), "r"(blo), "n"(SD), "n"(BHI), "n"(BOFF));
}

template <int I> struct IC { static constexpr int v = I; };
template <int B, int E, class F> __device__ __forceinline__ void static_for(F&& f) {
  if constexpr (B < E) { f(IC<B>{}); static_for<B + 1, E>(f); }
}

__device__ __forceinline__ uint32_t item_off(int it) { return (uint32_t)(it / OPER) * OPAGE + (uint32_t)(it % OPER) * OITEM; }
__device__ __forceinline__ uint32_t tile_off(uint32_t ioff, int rg, int c, uint32_t np) {
  const uint32_t c0 = ioff + (uint32_t)(rg * 3 + c) * 8192;
  return c0 + ((((uint32_t)__popc(c0 & L2_HASH) ^ np) & 1u) << 12);
}

__device__ __forceinline__ constexpr bool seq_is_m(int i) {
  return i >= P2_BEG ? ((i - P2_BEG) & 1) == 0 : ((i % 26) < 20 && ((i % 26) & 1) == 0);
}

__device__ __forceinline__ void softmax96(const float* s, uint32_t* p, float& l0, float& l1) {
  constexpr float C = 0.07216878364870322f * 1.4426950408889634f;
  float m0 = fmaxf(s[0], s[1]), m1 = fmaxf(s[2], s[3]);
#pragma unroll
  for (int j = 1; j < 12; j++) {
    m0 = fmaxf(m0, fmaxf(s[4 * j], s[4 * j + 1]));
    m1 = fmaxf(m1, fmaxf(s[4 * j + 2], s[4 * j + 3]));
  }
  m0 = fmaxf(m0, __shfl_xor_sync(0xffffffffu, m0, 1));
  m1 = fmaxf(m1, __shfl_xor_sync(0xffffffffu, m1, 1));
  m0 = fmaxf(m0, __shfl_xor_sync(0xffffffffu, m0, 2));
  m1 = fmaxf(m1, __shfl_xor_sync(0xffffffffu, m1, 2));
  const float b0 = -m0 * C, b1 = -m1 * C;
  l0 = 0.f; l1 = 0.f;
#pragma unroll
  for (int j = 0; j < 12; j++) {
    const float e0 = ex2(fmaf(s[4 * j], C, b0)), e1 = ex2(fmaf(s[4 * j + 1], C, b0));
    const float e2 = ex2(fmaf(s[4 * j + 2], C, b1)), e3 = ex2(fmaf(s[4 * j + 3], C, b1));
    l0 += e0 + e1;
    l1 += e2 + e3;
    p[2 * j]     = pack_bf16(e0, e1);
    p[2 * j + 1] = pack_bf16(e2, e3);
  }
}

template <bool BY_SMID> __device__ __forceinline__ int cluster_role() {
  if (!BY_SMID) { const int cl = blockIdx.x >> 1; return cl < 64 ? cl : -1; }
  uint32_t smid;
  asm volatile("mov.u32 %0, %%smid;" : "=r"(smid));
  const int tpc = (int)(smid >> 1);
  const int t2 = tpc - 32;
  const int q7 = (t2 * 37) >> 8;
  const int mid = (1 + t2 - 7 * q7) * 8 + 4 + q7;
  const int hi = tpc == 60 ? 4 : tpc == 62 ? 5 : tpc == 64 ? 6 : tpc == 65 ? 7 : -1;
  const int role = tpc < 32 ? (tpc & 7) * 8 + (tpc >> 3) : tpc < 60 ? mid : hi;
  return __shfl_sync(0xffffffffu, role, 0);
}

template <bool BY_SMID>
__global__ void __launch_bounds__(512, 1) fused_kernel(const __grid_constant__ Params prm) {
  extern __shared__ uint8_t smem_raw[];
  if (threadIdx.x == 384) {
    asm volatile("prefetch.tensormap [%0];" ::"l"(&prm.wq[0]) : "memory");
    asm volatile("prefetch.tensormap [%0];" ::"l"(&prm.wq[1]) : "memory");
    asm volatile("prefetch.tensormap [%0];" ::"l"(&prm.x[0]) : "memory");
    asm volatile("prefetch.tensormap [%0];" ::"l"(&prm.x[1]) : "memory");
  }
  const uint32_t base = __shfl_sync(0xffffffffu, (smem_u32(smem_raw) + 1023) & ~1023u, 0);
  const uint32_t bars = base + BAR_OFF;
  const uint32_t obar = bars + 3 * NSLOT * 8;
  const uint32_t hbar = obar + 8;
  const uint32_t pbar = hbar + 64;
  const uint32_t tbar = pbar + 8;
  const uint32_t cbar = tbar + 8;
  const uint32_t xrecv = bars + 1088;
  const uint32_t tagw = bars + 504;
  const uint32_t otab = bars + 640;
  const uint32_t itab = otab + 144;
  const int tid = threadIdx.x;
  const bool is_producer = __shfl_sync(0xffffffffu, tid >> 7, 0) == 3;

  uint32_t rank;
  asm("mov.u32 %0, %%cluster_ctarank;" : "=r"(rank));
  rank = __shfl_sync(0xffffffffu, rank, 0);
  const int role = cluster_role<BY_SMID>();
  if (role < 0) return;
#define ROLE_VARS(role_)                                                                                              \
  const int grp = (role_) >> 3, idx = (role_) & 7;                                                                    \
  const int cta = (role_) * 2 + (int)rank;                                                         \
  const int p = idx & 3;                                                                               \
  const int g = grp & 3;                           \
  const int br = grp >> 2;                                                                                 \
  const int j = (idx >> 2) * 2 + (int)rank;                       \
  (void)cta; (void)p; (void)g; (void)br; (void)j

  {
    const int w = __shfl_sync(0xffffffffu, tid >> 5, 0);
    if (elect_one()) {
      mbar_init(bars + w * 8, w < 9 ? 1 : 6);
      mbar_init(bars + (w + 16) * 8, w < 2 ? 6 : w < 11 ? 3 : w == 11 ? 12 : 1);
      if (w < 7) mbar_init(bars + (w + 32) * 8, 1);
      asm volatile("fence.mbarrier_init.release.cluster;" ::: "memory");
    }
  }
  __syncthreads();
  asm volatile("barrier.cluster.arrive.relaxed.aligned;" ::: "memory");

  if (is_producer) {
    asm volatile("setmaxnreg.dec.sync.aligned.u32 32;");
    const int role_p = cluster_role<BY_SMID>();
    ROLE_VARS(role_p);
    const int warp = __shfl_sync(0xffffffffu, (tid >> 5) & 3, 0);
    if (warp == 0) {
      const CUtensorMap* mw = &prm.wq[br];
      const CUtensorMap* mk = &prm.k[br];
      const CUtensorMap* mv = &prm.v[br];
      const CUtensorMap* mo = &prm.wo[br];
      const uint64_t pol = policy_evict_first();
      const uint32_t ebar = bars + 2 * NSLOT * 8;
      if (elect_one()) {
        mbar_expect_tx(bars + 1 * 8, SLOT);
        tma3h(base + 1 * SLOT, mw, bars + 1 * 8, 0, 0, (g * 4 + j) * 3, pol);
      }
      __syncwarp();
      asm volatile("barrier.cluster.wait.acquire.aligned;" ::: "memory");
      if (elect_one()) {
#pragma unroll
        for (int ks = 1; ks < 4; ks++) {
          const uint32_t s = 2 * ks + 1;
          mbar_expect_tx(bars + s * 8, SLOT);
          tma3h(base + s * SLOT, mw, bars + s * 8, 0, ks * 64, (g * 4 + j) * 3, pol);
        }
        asm volatile("prefetch.tensormap [%0];" ::"l"(mk) : "memory");
        asm volatile("prefetch.tensormap [%0];" ::"l"(mv) : "memory");
      }
      __syncwarp();
      uint32_t slot = 0, par = 0;
      auto acquire = [&]() { mbar_wait(ebar + slot * 8, (par >> slot) & 1); par ^= 1u << slot; };
      auto adv = [&](uint32_t d) { slot += d; if (slot >= NSLOT) slot -= NSLOT; };
#pragma unroll 1
      for (int rnd = 0; rnd < 2; rnd++) {
        const int head = rnd * 16 + g * 4 + j;
#pragma unroll 1
        for (int ks = rnd == 0 ? 4 : 0; ks < 10; ks++) {
          acquire();
          if (elect_one()) {
            mbar_expect_tx(bars + slot * 8, SLOT);
            tma3h(base + slot * SLOT, mw, bars + slot * 8, 0, ks * 64, head * 3, pol);
          }
          adv(ks == 9 ? 1 : 2);
        }
#pragma unroll 1
        for (int c = 0; c < 3; c++) {
          acquire();
          if (elect_one()) {
            mbar_expect_tx(bars + slot * 8, SLOT);
            tma4h(base + slot * SLOT, mk, bars + slot * 8, c * 64, 0, head, 2 * p, pol);
          }
          adv(1);
        }
#pragma unroll 1
        for (int c = 0; c < 3; c++) {
          acquire();
          if (elect_one()) {
            const int b0 = c == 2 ? 1 : 0, k0 = c == 0 ? 0 : c == 1 ? 64 : 32;
            const int b1 = c == 0 ? 0 : 1, k1 = c == 0 ? 32 : c == 1 ? 0 : 64;
            mbar_expect_tx(bars + slot * 8, SLOT);
            tma4h(base + slot * SLOT,         mv, bars + slot * 8, 0, k0, 0, (2 * p + b0) * NH + head, pol);
            tma4h(base + slot * SLOT + 12288, mv, bars + slot * 8, 0, k1, 0, (2 * p + b1) * NH + head, pol);
          }
          adv(c == 2 ? 2 : 1);
        }
      }
#pragma unroll 1
      for (int t = 0; t < 24; t++) {
        const int hh = t / 3;
        const int k0 = ((hh >> 2) * 16 + g * 4 + ((hh & 3) ^ (j & 2))) * DH + (t - hh * 3) * 64;
        acquire();
        if (elect_one()) {
          mbar_expect_tx(bars + slot * 8, 20480);
#pragma unroll
          for (int c = 0; c < 5; c++) tma5h(base + slot * SLOT + c * 4096, mo, bars + slot * 8, j * 160 + c * 32, 0, 0, 0, k0 >> 5, pol);
        }
        adv(2);
      }
    } else if (warp == 1) {
      asm volatile("barrier.cluster.wait.acquire.aligned;" ::: "memory");
      const CUtensorMap* mx = &prm.x[br];
      const uint32_t ebar = bars + NSLOT * 8;
      const uint32_t half = rank * 12288;
      uint32_t slot = 0, par = 0;
      auto acquire = [&]() { mbar_wait(ebar + slot * 8, (par >> slot) & 1); par ^= 1u << slot; };
      auto adv = [&](uint32_t d) { slot += d; if (slot >= NSLOT) slot -= NSLOT; };
#pragma unroll 1
      for (int rnd = 0; rnd < 2; rnd++) {
#pragma unroll 1
        for (int ks = 0; ks < 10; ks++) {
          if (rnd != 0 || ks >= 5) acquire();
          if (elect_one()) {
            mbar_expect_tx(bars + slot * 8, SLOT);
            tma2_mc(base + slot * SLOT + half, mx, bars + slot * 8, ks * 64, p * 192 + (int)rank * 96);
          }
          adv(ks == 9 ? 8 : 2);
        }
      }
#pragma unroll 1
      for (int t = 0; t < 24; t++) {
        const int hh = t / 3;
        acquire();
        if (t - hh * 3 == 0) mbar_wait(hbar + hh * 8, 0);
        uint32_t row[3];
#pragma unroll
        for (int i = 0; i < 3; i++) asm volatile("ld.shared.u32 %0, [%1];" : "=r"(row[i]) : "r"(itab + (t * 3 + i) * 4) : "memory");
        if (elect_one()) {
          mbar_expect_tx(bars + slot * 8, SLOT);
#pragma unroll
          for (int i = 0; i < 3; i++) tma2_mc(base + slot * SLOT + half + i * 4096, &prm.o, bars + slot * 8, 0, (int)row[i]);
        }
        adv(2);
      }
    } else if (warp == 2) {
      asm volatile("barrier.cluster.wait.acquire.aligned;" ::: "memory");
      const int lane = tid & 31;
      unsigned tag;
      asm volatile("ld.relaxed.gpu.global.u32 %0, [%1];" : "=r"(tag) : "l"(&g_epoch) : "memory");
      tag = (tag + 1) & 0x7FFFFFFFu;
      if (lane == 0) {
        if (atomicInc(&g_done + (tag & prm.zero), 127u) == 127u) asm volatile("st.relaxed.gpu.global.u32 [%0], %1;" ::"l"(&g_epoch), "r"(tag) : "memory");
        asm volatile("st.shared.u32 [%0], %1;" ::"r"(tagw), "r"(tag) : "memory");
      }
      const int it0 = (br * 4 + p) * NH + g * 4;
      uint32_t npm = 0;
#pragma unroll 1
      for (int rnd = 0; rnd < 2; rnd++) {
        const int it = it0 + rnd * 16 + j;
        uint32_t np = 0;
        if (lane == 0) {
          const uint32_t po = (uint32_t)(it / OPER) * OPAGE + OPER * OITEM + (uint32_t)(it % OPER) * 128;
          uint8_t* line = prm.oscr + po;
          reinterpret_cast<uint4*>(line)[0] = make_uint4(0, 0, 0, 0);        reinterpret_cast<uint4*>(line)[1] = make_uint4(0, 0, 0, 0);
          reinterpret_cast<uint4*>(line + 4096)[0] = make_uint4(0, 0, 0, 0); reinterpret_cast<uint4*>(line + 4096)[1] = make_uint4(0, 0, 0, 0);
          uint32_t best0 = ~0u, best1 = ~0u;
#pragma unroll 1
          for (int rep = 0; rep < 8; rep++) {
            const uint32_t t0 = (uint32_t)clock64();
            uint32_t v;
            asm volatile("atom.relaxed.gpu.global.exch.b32 %0, [%1], %2;" : "=r"(v) : "l"(line + (rep & 1) * 4096), "r"(rep) : "memory");
            if (v > 7u) asm volatile("trap;");
            const uint32_t dt = (uint32_t)clock64() - t0;
            if (rep & 1) best1 = min(best1, dt); else best0 = min(best0, dt);
          }
          np = __popc((po + (best0 <= best1 ? 0 : 4096)) & L2_HASH) & 1;
        }
        np = __shfl_sync(0xffffffffu, np, 0);
        npm |= np << rnd;
        if (lane < 18)
          asm volatile("st.shared.u32 [%0], %1;" ::"r"(otab + (rnd * 18 + lane) * 4), "r"(tile_off(item_off(it), lane / 3, lane % 3, np)) : "memory");
      }
      __syncwarp();
      if (lane == 0) { mbar_arrive(pbar); }
#pragma unroll 1
      for (int rnd = 0; rnd < 2; rnd++) {
        mbar_wait(obar, rnd);
        if (lane == 0) {
          asm volatile("fence.acq_rel.gpu;" ::: "memory");
          asm volatile("st.relaxed.gpu.global.u32 [%0], %1;" ::"l"(&g_flag[it0 + rnd * 16 + j]), "r"(tag * 2 + ((npm >> rnd) & 1)) : "memory");
        }
        uint32_t done = 0;
        for (uint32_t spin = 0; done != 15u; spin++) {
          unsigned v;
          asm volatile("ld.acquire.gpu.global.u32 %0, [%1];" : "=r"(v) : "l"(&g_flag[it0 + rnd * 16 + (lane & 3)]) : "memory");
          uint32_t fresh = __ballot_sync(0xffffffffu, (v >> 1) == tag) & 15u & ~done;
          if (fresh) {
            asm volatile("fence.proxy.async.global;" ::: "memory");
            done |= fresh;
            while (fresh) {
              const int h4 = __ffs(fresh) - 1;
              fresh &= fresh - 1;
              const unsigned vh = __shfl_sync(0xffffffffu, v, h4);
              const int pos = h4 ^ (j & 2);
              if (lane < 9)
                asm volatile("st.shared.u32 [%0], %1;" ::"r"(itab + ((rnd * 4 + pos) * 9 + lane) * 4),
                             "r"(tile_off(item_off(it0 + rnd * 16 + h4), 3 * (int)rank + lane % 3, lane / 3, vh & 1u) >> 7) : "memory");
              __syncwarp();
              if (lane == 0) { mbar_arrive(hbar + (rnd * 4 + pos) * 8); }
            }
          } else {
            if (spin > SPIN_LIMIT) asm volatile("trap;");
            __nanosleep(100);
          }
        }
      }
      {
        const int sl = min(lane / 6, 2), wp = lane % 6;
        const int gs = (g + sl + 1) & 3;
        const int its = (br * 4 + p) * NH + gs * 4 + j;
        unsigned v;
        for (uint32_t spin = 0;; spin++) {
          asm volatile("ld.acquire.gpu.global.u32 %0, [%1];" : "=r"(v) : "l"(&g_flag[its]) : "memory");
          if (__all_sync(0xffffffffu, (v >> 1) == tag)) break;
          if (spin > SPIN_LIMIT) asm volatile("trap;");
          __nanosleep(100);
        }
        if (lane < 18)
          asm volatile("st.shared.u32 [%0], %1;" ::"r"(xrecv + lane * 4), "r"(tile_off(item_off(its), wp, (g - gs - 1) & 3, v & 1u)) : "memory");
      }
      mbar_wait(cbar, 0);
      if (lane == 0) asm volatile("st.relaxed.gpu.global.u32 [%0], %1;" ::"l"(&g_cons[cta]), "r"(tag) : "memory");
      for (uint32_t spin = 0;; spin++) {
        unsigned v;
        asm volatile("ld.acquire.gpu.global.u32 %0, [%1];" : "=r"(v) : "l"(&g_cons[(grp * 8 + p) * 2 + (lane & 1) + (lane & 2) * 4]) : "memory");
        if (__all_sync(0xffffffffu, v == tag)) break;
        if (spin > SPIN_LIMIT) asm volatile("trap;");
        __nanosleep(100);
      }
      __syncwarp();
      if (lane == 0) mbar_arrive(tbar);
    } else {
      asm volatile("barrier.cluster.wait.acquire.aligned;" ::: "memory");
      const int lane = tid & 31;
      const size_t kv_off = ((size_t)((2 * p + (lane >> 4)) * NH + g * 4 + j) * (SQ * DH)) * 2 + (lane & 15) * 256;
      const char* k_b = reinterpret_cast<const char*>(prm.kp[br]) + kv_off;
      const char* v_b = reinterpret_cast<const char*>(prm.vp[br]) + kv_off;
      const uint32_t pad = bars + 512 + lane * 4;
      long long next = clock64();
#pragma unroll 1
      for (int st = 0; st < 36; st++) {
        const int rnd = st / 18, c = st - rnd * 18;
        const char* q = (c < 9 ? k_b : v_b) + (c < 9 ? c : c - 9) * 4096 + rnd * (16 * SQ * DH * 2);
        asm volatile("cp.async.ca.shared.global.L2::256B [%0], [%1], 4;" ::"r"(pad), "l"(q) : "memory");
        next += st < PF_NA ? PF_A : st < PF_NB ? PF_B : PF_C;
        while (clock64() < next) __nanosleep(32);
      }
      asm volatile("cp.async.wait_all;" ::: "memory");
    }
    __syncwarp();
    asm volatile("barrier.cluster.arrive.relaxed.aligned;\nbarrier.cluster.wait.aligned;" ::: "memory");
  } else {
    asm volatile("setmaxnreg.inc.sync.aligned.u32 160;");
    uint32_t tid_c;
    asm volatile("mov.u32 %0, %%tid.x;" : "=r"(tid_c));
    const int wg = __shfl_sync(0xffffffffu, tid_c >> 7, 0);
    const int role_c = cluster_role<BY_SMID>();
    ROLE_VARS(role_c);
    asm volatile("barrier.cluster.wait.acquire.aligned;" ::: "memory");
    const int lane = tid & 31;
    const int warp = __shfl_sync(0xffffffffu, (tid >> 5) & 3, 0);
    const bool elect = (tid & 127) == 0;
    uint32_t rbars;
    asm("mapa.shared::cluster.u32 %0, %1, %2;" : "=r"(rbars) : "r"(bars), "r"(rank ^ 1));
    auto wait_fill = [&](int i) { mbar_wait(bars + (i % NSLOT) * 8, (i / NSLOT) & 1); };
    auto release = [&](int i) {
      if (i + NSLOT < NSEQ) {
        if (seq_is_m(i + NSLOT)) {
          mbar_arrive(bars + (NSLOT + i % NSLOT) * 8);
          asm volatile("mbarrier.arrive.shared::cluster.b64 _, [%0];" ::"r"(rbars + (NSLOT + i % NSLOT) * 8) : "memory");
        } else {
          mbar_arrive(bars + (2 * NSLOT + i % NSLOT) * 8);
        }
      }
    };
    const uint32_t a_base = dlo(base + wg * 8192, 16);
    const uint32_t b_base = (base & 0x3FFFF) >> 4;
    const uint32_t k_base = b_base + (wg >> 1) * (12288 / 16);
    uint32_t op[48];
    uint32_t a_first = a_base;
    uint8_t* const o0 = prm.oscr + ((warp & 1) * 16 + (lane >> 2)) * 128 + (lane & 3) * 16;
    uint32_t otile = 0;
    auto store_o1 = [&](int rnd, int v) {
      const int a = v >> 1, h = v & 1;
      if (v == 0 && rnd == 0) mbar_wait(pbar, 0);
      if ((v & 3) == 0)
        asm volatile("ld.shared.u32 %0, [%1];" : "=r"(otile) : "r"(otab + (rnd * 18 + (wg * 2 + (warp >> 1)) * 3 + (a >> 1)) * 4) : "memory");
      uint4* d = reinterpret_cast<uint4*>(o0 + otile + (a & 1) * 64);
      d[h * 64] = make_uint4(op[8 * a + h], op[8 * a + 2 + h], op[8 * a + 4 + h], op[8 * a + 6 + h]);
      if (v == 11) { __syncwarp(); if (lane == 0) mbar_arrive(obar); }
    };
    auto store_o = [&](int rnd, auto KS, auto N) {
      static_for<12 * KS.v / N.v, (KS.v < N.v ? 12 * (KS.v + 1) / N.v : 0)>([&](auto V) { store_o1(rnd, V.v); });
    };

    static_for<0, 2>([&](auto RND) {
      constexpr int rnd = RND.v;
      constexpr int f0 = rnd * 26;
      float acc[96];
      static_for<0, 10>([&](auto KS) {
        constexpr int ks = KS.v;
        constexpr int fx = f0 + 2 * ks, fw = fx + 1;
        wait_fill(fx); wait_fill(fw);
        if constexpr (ks == 9) {
          if (wg != 1) {
            WG_WAIT(0);
            if (elect) { release(fx - 2); release(fw - 2); }
            if (wg == 0) asm volatile("bar.sync 1, 256;" ::: "memory");
            else         asm volatile("bar.sync 6, 256;" ::: "memory");
          }
        }
        WG_FENCE();
        static_for<0, 4>([&](auto KK) {
          constexpr int kk = KK.v;
          wg_ss_n192_tb<HI_SW128, HI_SW128, (fx % NSLOT) * (SLOT / 16) + kk * 2, (fw % NSLOT) * (SLOT / 16) + kk * 128 + LBO(8192), (ks | kk) != 0>(acc, (ks | kk) == 0 ? a_first : a_base, b_base);
        });
        WG_COMMIT();
        if constexpr (ks == 9) {
          if (wg == 1) asm volatile("bar.arrive 1, 256;" ::: "memory");
          if (wg == 0) asm volatile("bar.arrive 6, 256;" ::: "memory");
        }
        if constexpr (rnd == 1) store_o(0, KS, IC<O1_STEPS>{});
        if (ks > 0) {
          WG_WAIT(1);
          if (elect && !(ks == 9 && wg != 1)) { release(fx - 2); release(fw - 2); }
        }
      });
      WG_WAIT(0);
      fence_regs(acc);
      if (elect) { release(f0 + 18); release(f0 + 19); }

      uint32_t q[48];
#pragma unroll
      for (int i = 0; i < 48; i++) q[i] = pack_bf16(acc[2 * i], acc[2 * i + 1]);

      fence_regs(q);
      wait_fill(f0 + 20); wait_fill(f0 + 21); wait_fill(f0 + 22);
      float l0, l1;
      uint32_t pa[24];
      {
        float s[48];
        fence_regs(q);
        if (wg == 0) asm volatile("bar.sync 2, 256;" ::: "memory");
        if (wg == 2) asm volatile("bar.sync 3, 256;" ::: "memory");
        WG_FENCE();
        static_for<0, 12>([&](auto T) {
          constexpr int t = T.v;
          wg_rs_n96<HI_SW128, ((f0 + 20 + t / 4) % NSLOT) * (SLOT / 16) + (t % 4) * 2 + LBO(16), t != 0>(s, q[4 * t], q[4 * t + 1], q[4 * t + 2], q[4 * t + 3], k_base);
        });
        WG_COMMIT();
        if (wg == 0) asm volatile("bar.arrive 3, 256;" ::: "memory");
        WG_WAIT(0);
        fence_regs(s); fence_regs(q);
        if (wg == 1) {
          if (warp < 2) {
#pragma unroll
            for (int i = 0; i < 48; i++) q[i] = 0;
          }
          else {
#pragma unroll
            for (int i = 0; i < 48; i++) s[i] = 0.f;
          }
          fence_regs(s); fence_regs(q);
          WG_FENCE();
          static_for<0, 12>([&](auto T) {
            constexpr int t = T.v;
            wg_rs_n96<HI_SW128, (12288 / 16) + ((f0 + 20 + t / 4) % NSLOT) * (SLOT / 16) + (t % 4) * 2 + LBO(16), 1>(s, q[4 * t], q[4 * t + 1], q[4 * t + 2], q[4 * t + 3], b_base);
          });
          WG_COMMIT();
          asm volatile("bar.arrive 2, 256;" ::: "memory");
          WG_WAIT(0);
          fence_regs(s); fence_regs(q);
        }
        if (elect) { release(f0 + 20); release(f0 + 21); release(f0 + 22); }
        softmax96(s, pa, l0, l1);
      }

      wait_fill(f0 + 23); wait_fill(f0 + 24); wait_fill(f0 + 25);
      float oa[96];
      fence_regs(pa);
      WG_FENCE();
      static_for<0, 6>([&](auto T) {
        constexpr int t = T.v, pc = t / 2;
        constexpr uint32_t o_a = ((f0 + 23 + pc / 2) % NSLOT) * (SLOT / 16) + (pc % 2) * (12288 / 16);
        constexpr uint32_t o_b = ((f0 + 23 + (pc + 3) / 2) % NSLOT) * (SLOT / 16) + ((pc + 3) % 2) * (12288 / 16);
        wg_rs_n192_tb<HI_SW128, o_a + (t % 2) * 128 + LBO(4096), t != 0>(oa, pa[4 * t], pa[4 * t + 1], pa[4 * t + 2], pa[4 * t + 3],
                                                                        b_base + (wg == 2 ? o_b - o_a : 0u));
      });
      WG_COMMIT();
      l0 += __shfl_xor_sync(0xffffffffu, l0, 1);
      l1 += __shfl_xor_sync(0xffffffffu, l1, 1);
      l0 += __shfl_xor_sync(0xffffffffu, l0, 2);
      l1 += __shfl_xor_sync(0xffffffffu, l1, 2);
      const float r0 = 1.0f / l0, r1 = 1.0f / l1;
      WG_WAIT(0);
      fence_regs(oa); fence_regs(pa);
      if (wg == 1) {
        if (warp < 2) {
#pragma unroll
          for (int i = 0; i < 24; i++) pa[i] = 0;
        }
        else {
#pragma unroll
          for (int i = 0; i < 96; i++) oa[i] = 0.f;
        }
        fence_regs(oa); fence_regs(pa);
        WG_FENCE();
        static_for<0, 6>([&](auto T) {
          constexpr int t = T.v, pc = 3 + t / 2;
          wg_rs_n192_tb<HI_SW128, ((f0 + 23 + pc / 2) % NSLOT) * (SLOT / 16) + (pc % 2) * (12288 / 16) + (t % 2) * 128 + LBO(4096), 1>(oa, pa[4 * t], pa[4 * t + 1], pa[4 * t + 2], pa[4 * t + 3], b_base);
        });
        WG_COMMIT();
        WG_WAIT(0);
        fence_regs(oa); fence_regs(pa);
      }
      if (elect) { release(f0 + 23); release(f0 + 24); release(f0 + 25); }
#pragma unroll
      for (int b = 0; b < 24; b++) {
        op[2 * b]     = pack_bf16(oa[4 * b] * r0, oa[4 * b + 1] * r0);
        op[2 * b + 1] = pack_bf16(oa[4 * b + 2] * r1, oa[4 * b + 3] * r1);
      }
      {
        uint32_t d = 0;
#pragma unroll
        for (int i = 0; i < 48; i += 3) d |= op[i] | op[i + 1] | op[i + 2];
        a_first = a_base + (d & prm.zero);
      }
    });

    float acc[80];
    uint32_t tg, xo[3], xi[3], ooff;
    int ge;
    static_for<0, 24>([&](auto T) {
      constexpr int t = T.v;
      constexpr int fx = P2_BEG + 2 * t, fw = fx + 1;
      wait_fill(fx); wait_fill(fw);
      if constexpr (t == 21) {
        mbar_wait(tbar, 0);
        uint32_t tag;
        asm volatile("ld.shared.u32 %0, [%1];" : "=r"(tag) : "r"(tagw) : "memory");
        tg = (0x7F81u + tag % 126u) << 16;
#pragma unroll
        for (int sl = 0; sl < 3; sl++) {
          asm volatile("ld.shared.u32 %0, [%1];" : "=r"(xo[sl]) : "r"(otab + ((wg * 2 + (warp >> 1)) * 3 + ((-2 - sl) & 3)) * 4) : "memory");
          asm volatile("ld.shared.u32 %0, [%1];" : "=r"(xi[sl]) : "r"(xrecv + (sl * 6 + wg * 2 + (warp >> 1)) * 4) : "memory");
          xo[sl] += (warp & 1) * 1536 + lane * 16;
          xi[sl] += (warp & 1) * 1536 + lane * 16;
        }
        {
          const int role_e = cluster_role<BY_SMID>();
          ROLE_VARS(role_e);
          uint32_t tid_e;
          asm volatile("mov.u32 %0, %%tid.x;" : "=r"(tid_e));
          ge = g;
          ooff = (p * 192 + (tid_e >> 5) * 16 + ((tid_e & 31) >> 2)) * (2 * DM) + br * DM + j * 160 + g * 40 + (tid_e & 3) * 2;
        }
        if (wg == 1) asm volatile("bar.sync 4, 256;" ::: "memory");
        if (wg == 2) asm volatile("bar.sync 5, 256;" ::: "memory");
      }
      WG_FENCE();
      static_for<0, 4>([&](auto KK) {
        constexpr int kk = KK.v;
        wg_ss_n160_tb<HI_SW128, HI_SW64, (fx % NSLOT) * (SLOT / 16) + kk * 2, (fw % NSLOT) * (SLOT / 16) + kk * 64 + LBO(4096), (t | kk) != 0>(acc, (t | kk) == 0 ? a_first : a_base, b_base);
      });
      WG_COMMIT();
      if constexpr (t == 23) {
        if (wg == 0) asm volatile("bar.arrive 4, 256;" ::: "memory");
        if (wg == 1) asm volatile("bar.arrive 5, 256;" ::: "memory");
      }
      if constexpr (t == 12) { if (tid == 0) mbar_arrive(cbar); }
      store_o(1, T, IC<O2_STEPS>{});
      if (t > 0) {
        WG_WAIT(1);
        if (elect) { release(fx - 2); release(fw - 2); }
      }
    });
    WG_WAIT(0);
    fence_regs(acc);
    asm volatile("barrier.cluster.arrive.relaxed.aligned;" ::: "memory");
    {
    const int g = ge;
    {
#pragma unroll
      for (int sl = 0; sl < 3; sl++) {
        const int qsel = (g - 1 - sl) & 3;
        uint4* dst = reinterpret_cast<uint4*>(prm.oscr + xo[sl]);
#pragma unroll
        for (int qd = 0; qd < 4; qd++) {
          if (qd == qsel) {
#pragma unroll
            for (int v = 0; v < 3; v++) {
              const float* a = &acc[20 * qd + 7 * v];
              const uint32_t w0 = pack_bf16(a[0], a[1]), w1 = pack_bf16(a[2], a[3]), w2 = pack_bf16(a[4], a[5]);
              const uint32_t w3 = (pack_bf16(v < 2 ? a[v < 2 ? 6 : 0] : 0.f, 0.f) & 0xFFFFu) | tg;
              asm volatile("{\n.reg .b64 lo, hi;\n.reg .b128 q;\nmov.b64 lo, {%1, %2};\nmov.b64 hi, {%3, %4};\nmov.b128 q, {lo, hi};\n"
                           "st.relaxed.gpu.global.b128 [%0], q;\n}" ::"l"(dst + v * 32), "r"(w0), "r"(w1), "r"(w2), "r"(w3) : "memory");
            }
          }
        }
      }
      float own[20];
#pragma unroll
      for (int i = 0; i < 20; i++) own[i] = g == 0 ? acc[i] : g == 1 ? acc[20 + i] : g == 2 ? acc[40 + i] : acc[60 + i];
      uint32_t rv[9][4];
      const uint4* src[3];
#pragma unroll
      for (int sl = 0; sl < 3; sl++) src[sl] = reinterpret_cast<const uint4*>(prm.oscr + xi[sl]);
      auto fetch = [&](int sl) {
#pragma unroll
        for (int v = 0; v < 3; v++)
          asm volatile("{\n.reg .b64 lo, hi;\n.reg .b128 q;\nld.relaxed.gpu.global.b128 q, [%4];\nmov.b128 {lo, hi}, q;\n"
                       "mov.b64 {%0, %1}, lo;\nmov.b64 {%2, %3}, hi;\n}"
                       : "=r"(rv[sl * 3 + v][0]), "=r"(rv[sl * 3 + v][1]), "=r"(rv[sl * 3 + v][2]), "=r"(rv[sl * 3 + v][3]) : "l"(src[sl] + v * 32) : "memory");
      };
      auto missing = [&](int sl) { return (((rv[sl * 3][3] ^ tg) | (rv[sl * 3 + 1][3] ^ tg) | (rv[sl * 3 + 2][3] ^ tg)) >> 16) != 0; };
      if (lane < 3) {
        const uint32_t* w = reinterpret_cast<const uint32_t*>((lane == 0 ? src[0] : lane == 1 ? src[1] : src[2]) - lane + 2 * 32 + 31) + 3;
        uint32_t t;
        for (uint32_t spin = 0;; spin++) {
          asm volatile("ld.relaxed.gpu.global.u32 %0, [%1];" : "=r"(t) : "l"(w) : "memory");
          if ((t & 0xFFFF0000u) == tg || spin > SPIN_LIMIT) break;
          __nanosleep(64);
        }
      }
      __syncwarp();
      fetch(0); fetch(1); fetch(2);
      {
        uint32_t spin = 0;
        while (true) {
          const bool m0 = missing(0), m1 = missing(1), m2 = missing(2);
          if (!(m0 | m1 | m2) || ++spin > SPIN_LIMIT) break;
          __nanosleep(64);
          if (m0) fetch(0);
          if (m1) fetch(1);
          if (m2) fetch(2);
        }
      }
#pragma unroll
      for (int sl = 0; sl < 3; sl++) {
#pragma unroll
        for (int v = 0; v < 3; v++) {
          const uint32_t* w = rv[sl * 3 + v];
          own[7 * v + 0] += __uint_as_float(w[0] << 16); own[7 * v + 1] += __uint_as_float(w[0] & 0xFFFF0000u);
          own[7 * v + 2] += __uint_as_float(w[1] << 16); own[7 * v + 3] += __uint_as_float(w[1] & 0xFFFF0000u);
          own[7 * v + 4] += __uint_as_float(w[2] << 16); own[7 * v + 5] += __uint_as_float(w[2] & 0xFFFF0000u);
          if (v < 2) own[v < 2 ? 7 * v + 6 : 0] += __uint_as_float(w[3] << 16);
        }
      }
      __nv_bfloat16* o = prm.out + ooff;
#pragma unroll
      for (int b = 0; b < 5; b++) {
        *reinterpret_cast<uint32_t*>(o + b * 8) = pack_bf16(own[4 * b], own[4 * b + 1]);
        *reinterpret_cast<uint32_t*>(o + 8 * (2 * DM) + b * 8) = pack_bf16(own[4 * b + 2], own[4 * b + 3]);
      }
    }
    }
    asm volatile("barrier.cluster.wait.aligned;" ::: "memory");
  }
}

typedef CUresult (*EncodeFn)(CUtensorMap*, CUtensorMapDataType, cuuint32_t, void*, const cuuint64_t*, const cuuint64_t*, const cuuint32_t*,
                             const cuuint32_t*, CUtensorMapInterleave, CUtensorMapSwizzle, CUtensorMapL2promotion, CUtensorMapFloatOOBfill);

bool make_map(EncodeFn enc, CUtensorMap* m, const void* ptr, int rank, const uint64_t* dims, const uint64_t* strides, const uint32_t* box,
              CUtensorMapSwizzle sw) {
  cuuint64_t d[5], s[5];
  cuuint32_t b[5], es[5];
  for (int i = 0; i < rank; i++) { d[i] = dims[i]; b[i] = box[i]; es[i] = 1; }
  for (int i = 0; i + 1 < rank; i++) s[i] = strides[i];
  return enc(m, CU_TENSOR_MAP_DATA_TYPE_BFLOAT16, rank, const_cast<void*>(ptr), d, s, b, es, CU_TENSOR_MAP_INTERLEAVE_NONE, sw,
             CU_TENSOR_MAP_L2_PROMOTION_L2_128B, CU_TENSOR_MAP_FLOAT_OOB_FILL_NONE) == CUDA_SUCCESS;
}

}

extern "C" void kernel_launch(void* const* d_in, const int* in_sizes, int n_in, void* d_out, int out_size) {
  (void)in_sizes; (void)n_in; (void)out_size;
  static EncodeFn enc = nullptr;
  static void* oscr = nullptr;
  static uint32_t by_smid = 0;
  if (!enc) {
    void* fn = nullptr;
    cudaDriverEntryPointQueryResult st;
    cudaGetDriverEntryPoint("cuTensorMapEncodeTiled", &fn, cudaEnableDefault, &st);
    enc = (EncodeFn)fn;
    cudaGetSymbolAddress(&oscr, g_oscr);
    oscr = (void*)(((uintptr_t)oscr + OPAGE - 1) & ~(uintptr_t)(OPAGE - 1));
    cudaFuncSetAttribute(fused_kernel<true>, cudaFuncAttributeMaxDynamicSharedMemorySize, SMEM_DYN);
    cudaFuncSetAttribute(fused_kernel<false>, cudaFuncAttributeMaxDynamicSharedMemorySize, SMEM_DYN);
    int sms = 0;
    cudaDeviceGetAttribute(&sms, cudaDevAttrMultiProcessorCount, 0);
    by_smid = sms == 132;
  }
  Params prm;
  bool ok = true;
  for (int b = 0; b < 2; b++) {
    const void* x = d_in[b * 5 + 0];
    const void* k = d_in[b * 5 + 1];
    const void* v = d_in[b * 5 + 2];
    const void* wq = d_in[b * 5 + 3];
    const void* wo = d_in[b * 5 + 4];
    { uint64_t d[2] = {DM, ROWS}, s[1] = {DM * 2}; uint32_t bx[2] = {64, 96};
      ok &= make_map(enc, &prm.x[b], x, 2, d, s, bx, CU_TENSOR_MAP_SWIZZLE_128B); }
    { uint64_t d[3] = {64, DM, HD / 64}, s[2] = {HD * 2, 128}; uint32_t bx[3] = {64, 64, 3};
      ok &= make_map(enc, &prm.wq[b], wq, 3, d, s, bx, CU_TENSOR_MAP_SWIZZLE_128B); }
    { uint64_t d[4] = {DH, SQ, NH, NB}, s[3] = {DH * 2, SQ * DH * 2, NH * SQ * DH * 2}; uint32_t bx[4] = {64, 96, 1, 2};
      ok &= make_map(enc, &prm.k[b], k, 4, d, s, bx, CU_TENSOR_MAP_SWIZZLE_128B); }
    { uint64_t d[4] = {64, SQ, 3, NB * NH}, s[3] = {DH * 2, 128, SQ * DH * 2}; uint32_t bx[4] = {64, 32, 3, 1};
      ok &= make_map(enc, &prm.v[b], v, 4, d, s, bx, CU_TENSOR_MAP_SWIZZLE_128B); }
    { uint64_t d[5] = {DM, 2, 4, 4, HD / 32}, s[4] = {DM * 2, 8 * DM * 2, 2 * DM * 2, 32 * DM * 2}; uint32_t bx[5] = {32, 2, 4, 4, 2};
      ok &= make_map(enc, &prm.wo[b], wo, 5, d, s, bx, CU_TENSOR_MAP_SWIZZLE_64B); }
  }
  { uint64_t d[2] = {64, (uint64_t)OPAGES * (OPAGE / 128)}, s[1] = {128}; uint32_t bx[2] = {64, 32};
    ok &= make_map(enc, &prm.o, oscr, 2, d, s, bx, CU_TENSOR_MAP_SWIZZLE_128B); }
  for (int b = 0; b < 2; b++) { prm.kp[b] = (const __nv_bfloat16*)d_in[b * 5 + 1]; prm.vp[b] = (const __nv_bfloat16*)d_in[b * 5 + 2]; }
  prm.oscr = (uint8_t*)oscr;
  prm.zero = 0;
  prm.out = (__nv_bfloat16*)d_out;
  (void)ok;

  cudaLaunchConfig_t cfg = {};
  cfg.gridDim = dim3(by_smid ? 132 : 128);
  cfg.blockDim = dim3(512);
  cfg.dynamicSmemBytes = SMEM_DYN;
  cfg.stream = cudaStreamPerThread;
  cudaLaunchAttribute at[1];
  at[0].id = cudaLaunchAttributeClusterDimension;
  at[0].val.clusterDim.x = 2; at[0].val.clusterDim.y = 1; at[0].val.clusterDim.z = 1;
  cfg.attrs = at; cfg.numAttrs = 1;
  if (by_smid) cudaLaunchKernelEx(&cfg, fused_kernel<true>, prm);
  else         cudaLaunchKernelEx(&cfg, fused_kernel<false>, prm);
}
```
